```python
import torch

def _softmax(x, axis=-1):
    return torch.softmax(x, dim=axis)
def _gelu(x):
    return torch.nn.functional.gelu(x, approximate="tanh")
def _silu(x):
    return torch.nn.functional.silu(x)
def _sigmoid(x):
    return torch.sigmoid(x)
def _layernorm(x, axis=-1, eps=1e-5):
    m = x.mean(dim=axis, keepdim=True)
    v = x.var(dim=axis, keepdim=True, unbiased=False)
    return (x - m) / torch.sqrt(v + eps)
def _scatter_add(tgt, idx, src, axis=0):
    return tgt.clone().index_add_(axis, idx, src)
def _segment_sum(src, seg, n):
    out = torch.zeros((n,) + src.shape[1:], dtype=src.dtype)
    return out.index_add_(0, seg, src)
def _pad(x, pw):
    flat = tuple(v for pair in reversed(pw) for v in pair)
    return torch.nn.functional.pad(x, flat)

kernel_name = 'sequential_preLN__compressed_kv_cla__dense_activation_silu__decode'

def setup_inputs():

    _w = (lambda a: (lambda t: t.to(torch.bfloat16) if t.is_floating_point() else t)(torch.as_tensor(a)))
    def _A_setup():
        B, H, Sq, Sk, D, M = 1, 32, 1, 8192, 128, 576
        Dc = 4 * D
        return {
            "x": _w((lambda *s: torch.randn(*s, dtype=torch.bfloat16) * 0.05)(B, Sq, M)),
            "c_kv": _w((lambda *s: torch.randn(*s, dtype=torch.bfloat16) * 0.8)(B, Sk, Dc)),
            "w_q": _w((lambda *s: torch.randn(*s, dtype=torch.bfloat16) * 3.2)(M, H, D) * (M ** -0.5)),
            "w_uk": _w((lambda *s: torch.randn(*s, dtype=torch.bfloat16) * 3.2)(Dc, H, D) * (Dc ** -0.5)),
            "w_uv": _w((lambda *s: torch.randn(*s, dtype=torch.bfloat16) * 0.8)(Dc, H, D) * (Dc ** -0.5)),
            "w_o": _w((lambda *s: torch.randn(*s, dtype=torch.bfloat16) * 0.8)(H, D, M) * ((H * D) ** -0.5)),
        }
    _A_in = _A_setup()

    def _B_setup():
        B, S, D, F = 1, 1, 576, 4608
        return {
            "x": _w((lambda *s: torch.randn(*s, dtype=torch.bfloat16) * 0.05)(B, S, D)),
            "w1": _w((lambda *s: torch.randn(*s, dtype=torch.bfloat16) * 3.2)(D, F) * (D ** -0.5)),
            "w2": _w((lambda *s: torch.randn(*s, dtype=torch.bfloat16) * 0.2)(F, D) * (F ** -0.5)),
        }
    _B_in = _B_setup()

    return {
        "A_x": _A_in["x"],
        "A_c_kv": _A_in["c_kv"],
        "A_w_q": _A_in["w_q"],
        "A_w_uk": _A_in["w_uk"],
        "A_w_uv": _A_in["w_uv"],
        "A_w_o": _A_in["w_o"],
        "B_x": _B_in["x"],
        "B_w1": _B_in["w1"],
        "B_w2": _B_in["w2"],
    }

def reference(A_x, A_c_kv, A_w_q, A_w_uk, A_w_uv, A_w_o, B_x, B_w1, B_w2):
    def _A_ref(x, c_kv, w_q, w_uk, w_uv, w_o):
        B, Sq, M = x.shape[0], x.shape[1], x.shape[2]
        Sk = c_kv.shape[1]
        H, D = w_q.shape[1], w_q.shape[2]
        q = torch.einsum("bqm,mhd->bhqd", x, w_q)
        k = torch.einsum("bkc,chd->bhkd", c_kv, w_uk)
        v = torch.einsum("bkc,chd->bhkd", c_kv, w_uv)
        scores = torch.einsum("bhqd,bhkd->bhqk", q, k) * (D ** -0.5)
        off = Sk - Sq
        qi = torch.arange(Sq)[:, None]
        kj = torch.arange(Sk)[None, :]
        cmask = kj <= (qi + off)
        scores = torch.where(cmask[None, None], scores, -1e9)
        p = _softmax(scores, axis=-1)
        ctx = torch.einsum("bhqk,bhkd->bhqd", p, v)
        return torch.einsum("bhqd,hdm->bqm", ctx, w_o)

    def _B_ref(x, w1, w2):
        h = torch.einsum("bsd,df->bsf", x, w1)
        h = _silu(h)
        out = torch.einsum("bsf,fd->bsd", h, w2)
        return out

    x = A_x
    h = x + _A_ref(_layernorm(x, axis=-1), A_c_kv, A_w_q, A_w_uk, A_w_uv, A_w_o)
    h2 = h + _B_ref(_layernorm(h, axis=-1), B_w1, B_w2)
    return h2
```

```cpp
#include <cuda_runtime.h>
#include <cuda_bf16.h>
#include <cuda.h>
#include <stdint.h>

namespace {

constexpr int NH = 32, HD = 128, DM = 576, DC = 512, SK = 8192, DF = 4608;
constexpr int NCTA = 128;
constexpr int NPROD = 3;
constexpr int NTHREADS = 288 + 32 * NPROD;
constexpr int NC = 288;
constexpr int NRED = 36;

constexpr uint32_t OFF_WQ = 0;
constexpr uint32_t OFF_WUK = 36864;
constexpr uint32_t OFF_CK0 = 69632;
constexpr uint32_t OFF_CK1 = 135168;
constexpr uint32_t OFF_QA = 200704;
constexpr uint32_t OFF_W2 = OFF_CK0 + 40960;
constexpr uint32_t OFF_W1 = OFF_W2 + 46080;
constexpr uint32_t OFF_P = OFF_WQ + 32768;
constexpr uint32_t OFF_SG = OFF_QA + 2048;
constexpr uint32_t OFF_PB = 217088;
constexpr uint32_t OFF_CONST = 221184;
constexpr uint32_t OFF_VB = OFF_CONST + 704;
constexpr uint32_t VB_LO = 272, WS_LO = 144, HB_LO = 1168, H1_LO = 112;
constexpr uint32_t OFF_WS = OFF_VB + 544;
constexpr uint32_t OFF_SMAX = OFF_WS + 288;
constexpr uint32_t OFF_MX = OFF_SMAX + 512;
constexpr uint32_t OFF_CTXP = OFF_MX + 128;
constexpr uint32_t OFF_HB = OFF_CTXP + 512;
constexpr uint32_t OFF_QX = OFF_HB + HB_LO;
constexpr uint32_t OFF_ST = OFF_HB + 2336;
constexpr uint32_t OFF_H1 = OFF_ST + 144;
constexpr uint32_t OFF_TG = OFF_H1 + 208;
constexpr uint32_t OFF_BAR = OFF_TG + 8;
constexpr uint32_t SMEM_BYTES = OFF_BAR + 480;
static_assert(SMEM_BYTES <= 232448, "smem");
static_assert(OFF_BAR % 8 == 0 && OFF_SMAX % 16 == 0 && OFF_HB % 16 == 0 && OFF_ST % 16 == 0, "align");
static_assert(OFF_W2 % 1024 == 0 && OFF_W1 % 128 == 0 && OFF_W1 + 46080 + 16 <= OFF_PB, "layout");

constexpr int B_WUK = 0, B_CK = 4, B_WUV = 20, B_WO = 24, B_W1 = 33, B_W2 = 45, NOPS = 54;
constexpr int B_FREE_A = 54, B_FREE_B = 55, B_FREE_C0 = 56, B_CTX = 57, B_LATE = 58;

constexpr int PACE_NS_PER_KB = 42, PACE_PRE = 2, PACE_LAG = 12, LATE_NS = 190;
constexpr int Q_DELAY = 100;
constexpr int A_DELAY = 1200, A_MIN = 500, A_ABS = 5100;
constexpr int B_DELAY = 1100, B_MIN = 500, B_ABS = 9300, ML_DELAY = 400;
constexpr int H_DELAY = 800, F_DELAY = 300;

struct Scratch {
    uint32_t qp[NH * 4 * HD];
    uint32_t qa[NH * DC / 2];
    uint32_t part[NH * 4 * 64 * 64];
    uint32_t ml[NCTA * 64 * 32];
    uint32_t pp[NRED * NCTA * 32];
    uint32_t acc[224 * 32];
    uint32_t epoch[32];
};
__device__ __align__(1024) Scratch g_scratch;

__host__ __device__ constexpr uint64_t pack8(uint64_t a, uint64_t b, uint64_t c, uint64_t d, uint64_t e, uint64_t f) { return a | b << 8 | c << 16 | d << 24 | e << 32 | f << 40; }
__host__ __device__ constexpr uint64_t pack10(uint64_t a, uint64_t b, uint64_t c, uint64_t d, uint64_t e, uint64_t f) { return a | b << 10 | c << 20 | d << 30 | e << 40 | f << 50; }
static_assert(OFF_WUK % 512 == 0 && OFF_CK0 % 512 == 0 && OFF_W1 % 512 == 0 && OFF_W2 % 512 == 0, "op table granularity");
struct Maps { CUtensorMap m[6]; };

__device__ __forceinline__ uint32_t smem_u32(const void* p) { return (uint32_t)__cvta_generic_to_shared(p); }
__device__ __forceinline__ void mbar_init(uint32_t bar, uint32_t cnt) { asm volatile("mbarrier.init.shared::cta.b64 [%0], %1;" :: "r"(bar), "r"(cnt) : "memory"); }
__device__ __forceinline__ void mbar_expect_tx(uint32_t bar, uint32_t bytes) { asm volatile("mbarrier.arrive.expect_tx.shared::cta.b64 _, [%0], %1;" :: "r"(bar), "r"(bytes) : "memory"); }
__device__ __forceinline__ void mbar_arrive(uint32_t bar) { asm volatile("mbarrier.arrive.shared::cta.b64 _, [%0];" :: "r"(bar) : "memory"); }
__device__ __forceinline__ bool mbar_try(uint32_t bar) {
    uint32_t ok;
    asm volatile("{\n.reg .pred p;\nmbarrier.try_wait.parity.shared::cta.b64 p, [%1], 0;\nselp.u32 %0, 1, 0, p;\n}" : "=r"(ok) : "r"(bar) : "memory");
    return ok;
}
__device__ __noinline__ void mbar_wait(uint32_t bar) {
    for (int c = 0; !mbar_try(bar); c++) if (c > 4000000) __trap();
}
__device__ __forceinline__ void mbar_wait_inline(uint32_t bar) {
    asm volatile("{\n.reg .pred p;\n.reg .u32 c;\nmov.u32 c, 0;\n"
        "W%=:\nmbarrier.try_wait.parity.shared::cta.b64 p, [%0], 0;\n@p bra.uni D%=;\n"
        "add.u32 c, c, 1;\nsetp.lt.u32 p, c, 4000000;\n@p bra.uni W%=;\ntrap;\nD%=:\n}" :: "r"(bar) : "memory");
}
__device__ __forceinline__ void mbar_wait_cluster(uint32_t bar) {
    asm volatile("{\n.reg .pred p;\n.reg .u32 c;\nmov.u32 c, 0;\n"
        "W%=:\nmbarrier.try_wait.parity.acquire.cluster.shared::cta.b64 p, [%0], 0;\n@p bra.uni D%=;\n"
        "add.u32 c, c, 1;\nsetp.lt.u32 p, c, 4000000;\n@p bra.uni W%=;\ntrap;\nD%=:\n}" :: "r"(bar) : "memory");
}
__device__ __forceinline__ bool elect() {
    uint32_t p; asm volatile("{\n.reg .pred p;\nelect.sync _|p, 0xffffffff;\nselp.u32 %0, 1, 0, p;\n}" : "=r"(p)); return p;
}
__device__ __forceinline__ void tma3(uint32_t dst, const void* tm, int c0, int c1, int c2, uint32_t bar) {
    asm volatile("cp.async.bulk.tensor.3d.shared::cluster.global.mbarrier::complete_tx::bytes [%0], [%1, {%3, %4, %5}], [%2];"
        :: "r"(dst), "l"(tm), "r"(bar), "r"(c0), "r"(c1), "r"(c2) : "memory");
}
__device__ __forceinline__ void tma3_mc(uint32_t dst, const void* tm, int c0, int c1, int c2, uint32_t bar) {
    asm volatile("cp.async.bulk.tensor.3d.shared::cluster.global.mbarrier::complete_tx::bytes.multicast::cluster [%0], [%1, {%3, %4, %5}], [%2], %6;"
        :: "r"(dst), "l"(tm), "r"(bar), "r"(c0), "r"(c1), "r"(c2), "h"((uint16_t)3) : "memory");
}
__device__ __forceinline__ void bulk_store(void* dst, uint32_t src, uint32_t bytes) {
    asm volatile("cp.async.bulk.global.shared::cta.bulk_group [%0], [%1], %2;" :: "l"(dst), "r"(src), "r"(bytes) : "memory");
}
__device__ __forceinline__ void bulk_commit() { asm volatile("cp.async.bulk.commit_group;" ::: "memory"); }
__device__ __forceinline__ void bar_sync(int id, int n) { asm volatile("bar.sync %0, %1;" :: "r"(id), "r"(n) : "memory"); }
__device__ __forceinline__ void bar_arrive(int id, int n) { asm volatile("bar.arrive %0, %1;" :: "r"(id), "r"(n) : "memory"); }
__device__ __forceinline__ void fence_proxy_async() { asm volatile("fence.proxy.async.shared::cta;" ::: "memory"); }

__device__ __forceinline__ uint4 ld_poll4(const void* p) {
    uint4 v; asm volatile("ld.relaxed.gpu.global.v4.u32 {%0,%1,%2,%3}, [%4];" : "=r"(v.x), "=r"(v.y), "=r"(v.z), "=r"(v.w) : "l"(p) : "memory"); return v;
}
__device__ __forceinline__ uint2 ld_poll2(const void* p) {
    uint2 v; asm volatile("ld.relaxed.gpu.global.v2.u32 {%0,%1}, [%2];" : "=r"(v.x), "=r"(v.y) : "l"(p) : "memory"); return v;
}
__device__ __forceinline__ void st_pub4(void* p, uint4 v) {
    asm volatile("st.relaxed.gpu.global.v4.u32 [%0], {%1,%2,%3,%4};" :: "l"(p), "r"(v.x), "r"(v.y), "r"(v.z), "r"(v.w) : "memory");
}
__device__ __forceinline__ void st_pub2(void* p, uint32_t a, uint32_t b) {
    asm volatile("st.relaxed.gpu.global.v2.u32 [%0], {%1,%2};" :: "l"(p), "r"(a), "r"(b) : "memory");
}
__device__ __forceinline__ void st_pub1(void* p, uint32_t a) {
    asm volatile("st.relaxed.gpu.global.u32 [%0], %1;" :: "l"(p), "r"(a) : "memory");
}
__device__ __forceinline__ void red4(void* p, float a, float b, float c) {
    asm volatile("red.relaxed.gpu.global.add.v4.f32 [%0], {%1,%2,%3,%4};" :: "l"(p), "f"(a), "f"(b), "f"(c), "f"(1.f) : "memory");
}
__device__ __forceinline__ uint32_t nz(uint32_t w) { return max(w, 1u); }
__device__ __forceinline__ uint32_t nzf(float f) { return nz(__float_as_uint(f)); }
__device__ __forceinline__ uint32_t tagf(float f, uint32_t tag) { return (__float_as_uint(f) & ~1u) | tag; }
__device__ __forceinline__ bool tagged(const uint4& v, uint32_t tag) { const uint32_t m = tag ^ 1u; return ((v.x ^ m) & (v.y ^ m) & (v.z ^ m) & (v.w ^ m) & 1u) != 0; }
__device__ __forceinline__ uint32_t min4(const uint4& v) { return min(min(v.x, v.y), min(v.z, v.w)); }
__device__ __forceinline__ bool poll_done(bool ok, int& n) {
    if (__all_sync(~0u, ok)) return true;
    if (++n > 4000000) __trap();
    return false;
}

__device__ __forceinline__ uint32_t now_ns() { uint32_t t; asm volatile("mov.u32 %0, %%globaltimer_lo;" : "=r"(t)); return t; }
__device__ __noinline__ void wait_until(uint32_t t0, int ns) { while ((int)(now_ns() - t0) < ns) {} }
struct Quad { uint4 a, b, c, d; };
__device__ __forceinline__ Quad poll_quad_inl(Quad v, const uint32_t* p, int stride, uint32_t t0, int ns) {
    int n = 0;
    while (true) {
        const uint32_t ma = min4(v.a), mb = min4(v.b), mc = min4(v.c), md = min4(v.d);
        if (poll_done(min(min(ma, mb), min(mc, md)) != 0, n)) break;
        if (n == 1) while ((int)(now_ns() - t0) < ns) {}
        if (ma == 0) v.a = ld_poll4(p);
        if (mb == 0) v.b = ld_poll4(p + stride);
        if (mc == 0) v.c = ld_poll4(p + 2 * stride);
        if (md == 0) v.d = ld_poll4(p + 3 * stride);
    }
    return v;
}
__device__ __noinline__ Quad poll_quad(Quad v, const uint32_t* p, int stride, uint32_t t0, int ns) { return poll_quad_inl(v, p, stride, t0, ns); }
__device__ __forceinline__ Quad load_quad(const uint32_t* p, int stride) {
    Quad v; v.a = ld_poll4(p); v.b = ld_poll4(p + stride); v.c = ld_poll4(p + 2 * stride); v.d = ld_poll4(p + 3 * stride); return v;
}
__device__ __forceinline__ void ldsm4(uint32_t (&r)[4], uint32_t a) {
    asm volatile("ldmatrix.sync.aligned.m8n8.x4.shared.b16 {%0,%1,%2,%3}, [%4];" : "=r"(r[0]), "=r"(r[1]), "=r"(r[2]), "=r"(r[3]) : "r"(a) : "memory");
}
__device__ __forceinline__ void ldsm4t(uint32_t (&r)[4], uint32_t a) {
    asm volatile("ldmatrix.sync.aligned.m8n8.x4.trans.shared.b16 {%0,%1,%2,%3}, [%4];" : "=r"(r[0]), "=r"(r[1]), "=r"(r[2]), "=r"(r[3]) : "r"(a) : "memory");
}
__device__ __forceinline__ void ldsm2(uint32_t (&r)[2], uint32_t a) {
    asm volatile("ldmatrix.sync.aligned.m8n8.x2.shared.b16 {%0,%1}, [%2];" : "=r"(r[0]), "=r"(r[1]) : "r"(a) : "memory");
}
__device__ __forceinline__ void ldsm2t(uint32_t (&r)[2], uint32_t a) {
    asm volatile("ldmatrix.sync.aligned.m8n8.x2.trans.shared.b16 {%0,%1}, [%2];" : "=r"(r[0]), "=r"(r[1]) : "r"(a) : "memory");
}
__device__ __forceinline__ void stsm4(uint32_t a, uint32_t r0, uint32_t r1, uint32_t r2, uint32_t r3) {
    asm volatile("stmatrix.sync.aligned.m8n8.x4.shared.b16 [%0], {%1,%2,%3,%4};" :: "r"(a), "r"(r0), "r"(r1), "r"(r2), "r"(r3) : "memory");
}
__device__ __forceinline__ uint32_t pack_nz(float lo, float hi) {
    uint32_t r; asm("cvt.rn.bf16x2.f32 %0, %1, %2;" : "=r"(r) : "f"(hi), "f"(lo));
    asm("max.u16x2 %0, %0, %1;" : "+r"(r) : "r"(0x00010001u));
    return r;
}
__device__ __forceinline__ void stsm4t(uint32_t a, uint32_t r0, uint32_t r1, uint32_t r2, uint32_t r3) {
    asm volatile("stmatrix.sync.aligned.m8n8.x4.trans.shared.b16 [%0], {%1,%2,%3,%4};" :: "r"(a), "r"(r0), "r"(r1), "r"(r2), "r"(r3) : "memory");
}
__device__ __forceinline__ void mma16816(float (&d)[4], const uint32_t (&a)[4], uint32_t b0, uint32_t b1) {
    asm("mma.sync.aligned.m16n8k16.row.col.f32.bf16.bf16.f32 {%0,%1,%2,%3}, {%4,%5,%6,%7}, {%8,%9}, {%0,%1,%2,%3};"
        : "+f"(d[0]), "+f"(d[1]), "+f"(d[2]), "+f"(d[3]) : "r"(a[0]), "r"(a[1]), "r"(a[2]), "r"(a[3]), "r"(b0), "r"(b1));
}
__device__ __forceinline__ void mma1688(float (&d)[4], const uint32_t (&a)[2], uint32_t b0) {
    asm("mma.sync.aligned.m16n8k8.row.col.f32.bf16.bf16.f32 {%0,%1,%2,%3}, {%4,%5}, {%6}, {%0,%1,%2,%3};"
        : "+f"(d[0]), "+f"(d[1]), "+f"(d[2]), "+f"(d[3]) : "r"(a[0]), "r"(a[1]), "r"(b0));
}
__device__ __forceinline__ uint32_t pack_bf16(float lo, float hi) {
    uint32_t r; asm("cvt.rn.bf16x2.f32 %0, %1, %2;" : "=r"(r) : "f"(hi), "f"(lo)); return r;
}
__device__ __forceinline__ float bf_lo(uint32_t w) { return __uint_as_float(w << 16); }
__device__ __forceinline__ float bf_hi(uint32_t w) { return __uint_as_float(w & 0xffff0000u); }
__device__ __forceinline__ void split2(float a, float b, uint32_t& hi, uint32_t& lo) {
    hi = pack_bf16(a, b);
    lo = pack_bf16(a - bf_lo(hi), b - bf_hi(hi));
}
__device__ __forceinline__ float ex2(float x) { float y; asm("ex2.approx.ftz.f32 %0, %1;" : "=f"(y) : "f"(x)); return y; }
__device__ __forceinline__ uint32_t lds32(uint32_t a) { uint32_t v; asm volatile("ld.shared.u32 %0, [%1];" : "=r"(v) : "r"(a) : "memory"); return v; }
__device__ __forceinline__ float ldsf(uint32_t a) { float v; asm volatile("ld.shared.f32 %0, [%1];" : "=f"(v) : "r"(a) : "memory"); return v; }
__device__ __forceinline__ float2 ldsf2(uint32_t a) { float2 v; asm volatile("ld.shared.v2.f32 {%0,%1}, [%2];" : "=f"(v.x), "=f"(v.y) : "r"(a) : "memory"); return v; }
__device__ __forceinline__ float4 ldsf4(uint32_t a) { float4 v; asm volatile("ld.shared.v4.f32 {%0,%1,%2,%3}, [%4];" : "=f"(v.x), "=f"(v.y), "=f"(v.z), "=f"(v.w) : "r"(a) : "memory"); return v; }
__device__ __forceinline__ uint4 lds128(uint32_t a) { uint4 v; asm volatile("ld.shared.v4.u32 {%0,%1,%2,%3}, [%4];" : "=r"(v.x), "=r"(v.y), "=r"(v.z), "=r"(v.w) : "r"(a) : "memory"); return v; }
__device__ __forceinline__ void sts32(uint32_t a, uint32_t v) { asm volatile("st.shared.u32 [%0], %1;" :: "r"(a), "r"(v) : "memory"); }
__device__ __forceinline__ void sts64(uint32_t a, uint32_t v, uint32_t w) { asm volatile("st.shared.v2.u32 [%0], {%1,%2};" :: "r"(a), "r"(v), "r"(w) : "memory"); }
__device__ __forceinline__ void stsf(uint32_t a, float v) { asm volatile("st.shared.f32 [%0], %1;" :: "r"(a), "f"(v) : "memory"); }
__device__ __forceinline__ void stsf2(uint32_t a, float v, float w) { asm volatile("st.shared.v2.f32 [%0], {%1,%2};" :: "r"(a), "f"(v), "f"(w) : "memory"); }
__device__ __forceinline__ void stsf4(uint32_t a, float x, float y, float z, float w) { asm volatile("st.shared.v4.f32 [%0], {%1,%2,%3,%4};" :: "r"(a), "f"(x), "f"(y), "f"(z), "f"(w) : "memory"); }
__device__ __forceinline__ void sts128(uint32_t a, uint4 v) { asm volatile("st.shared.v4.u32 [%0], {%1,%2,%3,%4};" :: "r"(a), "r"(v.x), "r"(v.y), "r"(v.z), "r"(v.w) : "memory"); }

constexpr uint32_t DESC_HI = 64u | (1u << 30);
__device__ __forceinline__ uint32_t desc_lo(uint32_t addr) { return ((addr & 0x3FFFFu) >> 4) | (64u << 16); }
template <int TRANS_A>
__device__ __forceinline__ void wgmma16(float (&d)[8], uint32_t da, uint32_t db, int accumulate) {
    asm volatile("{\n.reg .pred p;\n.reg .b64 a, b;\nsetp.ne.b32 p, %10, 0;\nmov.b64 a, {%8, %12};\nmov.b64 b, {%9, %12};\n"
        "wgmma.mma_async.sync.aligned.m64n16k16.f32.bf16.bf16 {%0,%1,%2,%3,%4,%5,%6,%7}, a, b, p, 1, 1, %11, 0;\n}"
        : "+f"(d[0]), "+f"(d[1]), "+f"(d[2]), "+f"(d[3]), "+f"(d[4]), "+f"(d[5]), "+f"(d[6]), "+f"(d[7])
        : "r"(da), "r"(db), "r"(accumulate), "n"(TRANS_A), "n"(DESC_HI));
}
__device__ __forceinline__ void wg_fence() { asm volatile("wgmma.fence.sync.aligned;" ::: "memory"); }
__device__ __forceinline__ void wg_commit() { asm volatile("wgmma.commit_group.sync.aligned;" ::: "memory"); }
__device__ __forceinline__ void wg_wait0() { asm volatile("wgmma.wait_group.sync.aligned 0;" ::: "memory"); }
template <int N> __device__ __forceinline__ void pin(float (&d)[N]) {
#pragma unroll
    for (int i = 0; i < N; i++) asm volatile("" : "+f"(d[i]) :: "memory");
}


__device__ __forceinline__ void open_late_gate(uint32_t sb) {
    uint32_t now; asm volatile("mov.u32 %0, %%globaltimer_lo;" : "=r"(now));
    sts32(sb + OFF_TG, now);
    mbar_arrive(sb + OFF_BAR + 8 * B_LATE);
}
__device__ __noinline__ float reduce_slice(uint4 v, uint4 u, const uint32_t* p, uint32_t scratch, uint32_t tag, int tid, uint32_t t0, int ns) {
    int n = 0;
    while (!poll_done(tagged(v, tag) && tagged(u, tag), n)) {
        if (n == 1) while ((int)(now_ns() - t0) < ns) {}
        if (!tagged(v, tag)) v = ld_poll4(p);
        if (!tagged(u, tag)) u = ld_poll4(p + 64 * 32);
    }
    float a0 = __uint_as_float(v.x) + __uint_as_float(u.x), a1 = __uint_as_float(v.y) + __uint_as_float(u.y);
    float a2 = __uint_as_float(v.z) + __uint_as_float(u.z), a3 = __uint_as_float(v.w) + __uint_as_float(u.w);
#pragma unroll
    for (int o = 4; o <= 16; o <<= 1) {
        a0 += __shfl_xor_sync(~0u, a0, o); a1 += __shfl_xor_sync(~0u, a1, o);
        a2 += __shfl_xor_sync(~0u, a2, o); a3 += __shfl_xor_sync(~0u, a3, o);
    }
    if ((tid & 31) < 4) stsf4(scratch + ((tid >> 5) * 16 + (tid & 3) * 4) * 4, a0, a1, a2, a3);
    bar_sync(6, 256);
    float s = 0.f;
#pragma unroll
    for (int w = 0; w < 8; w++) s += ldsf(scratch + (w * 16 + (tid & 15)) * 4);
    return s;
}

__device__ __forceinline__ void publish_stats(float a, float b, float c, float d, uint32_t sb, int tid) {
    float s = (a + b) + (c + d), q = a * a + b * b + c * c + d * d;
#pragma unroll
    for (int o = 16; o; o >>= 1) { s += __shfl_xor_sync(~0u, s, o); q += __shfl_xor_sync(~0u, q, o); }
    if ((tid & 31) == 0) stsf2(sb + OFF_ST + (tid >> 5) * 8, s, q);
}
__device__ __forceinline__ float2 ln_stats(uint32_t sb) {
    float s = 0.f, q = 0.f;
#pragma unroll
    for (int w = 0; w < 7; w++) { const float2 u = ldsf2(sb + OFF_ST + w * 8); s += u.x; q += u.y; }
    const float mean = s * (1.f / DM);
    return make_float2(mean, rsqrtf(fmaxf(q * (1.f / DM) - mean * mean, 0.f) + 1e-5f));
}

template <int KSTEPS16, bool TAIL8>
__device__ __forceinline__ void out_proj_load(uint32_t (&a)[4][KSTEPS16][4], uint32_t (&a8)[4][2], uint32_t box, int mat, int r8) {
    const uint32_t base = box + ((mat >> 1) * 8 + r8) * 128 + (((mat & 1) ^ r8) << 4);
#pragma unroll
    for (int t = 0; t < 4; t++) {
#pragma unroll
        for (int s = 0; s < KSTEPS16; s++) ldsm4t(a[t][s], (base ^ (t << 5)) + s * 2048);
        if (TAIL8) ldsm2t(a8[t], ((box + r8 * 128 + (((mat & 1) ^ r8) << 4)) ^ (t << 5)) + KSTEPS16 * 2048);
    }
}

__global__ void __cluster_dims__(2, 1, 1) __launch_bounds__(NTHREADS, 1)
fused_decode_kernel(const __grid_constant__ Maps maps, const uint2* __restrict__ x, const uint8_t* __restrict__ wq, __nv_bfloat16* __restrict__ out, Scratch* __restrict__ G) {
    extern __shared__ __align__(1024) uint8_t smem_raw[];
    uint32_t sb;
    asm volatile("mov.u32 %0, %1;" : "=r"(sb) : "r"(smem_u32(smem_raw)));
    const int tid = threadIdx.x, lane = tid & 31;
    const int warp = __shfl_sync(~0u, tid >> 5, 0);
    int b; asm volatile("mov.u32 %0, %%ctaid.x;" : "=r"(b));
    const int kap = b >> 1, r = b & 1, h = b >> 2, j = b & 3;
    const uint32_t bars = sb + OFF_BAR;
    const int red = b < NRED ? b : NRED;
    const uint32_t t_kernel = now_ns();

    if (warp >= 9 && warp < 9 + NPROD) {
        const uint32_t t0 = t_kernel;
        const int k = NPROD * lane + (warp - 9);
        if (lane == 0) {
            if (sb & 1023u) __trap();
            mbar_init(bars + 8 * k, 1);
            asm volatile("fence.mbarrier_init.release.cluster;" ::: "memory");
            mbar_expect_tx(bars + 8 * k, 8192u);
            asm volatile("prefetch.tensormap [%0];" :: "l"(&maps.m[k]) : "memory");
            asm volatile("prefetch.tensormap [%0];" :: "l"(&maps.m[3 + k]) : "memory");
        }
        const int js = k - B_W1, jq = js / 3, jr = js - 3 * jq;
        const int map = k < B_W1 ? (k >= B_CK) + (k >= B_WUV) + (k >= B_WO) : (js >= 18 || jr == 2) ? 5 : 4;
        const int il = js >= 18 ? js - 12 : jr == 2 ? jq : 2 * jq + jr;
        auto lut8 = [&](uint64_t v) { return (uint32_t)(v >> (8 * map)) & 0xFFu; };
        auto lut10 = [&](uint64_t v) { return (uint32_t)(v >> (10 * map)) & 0x3FFu; };
        const int i = k < B_W1 ? k - (int)lut8(pack8(B_WUK, B_CK, B_WUV, B_WO, 0, 0)) : il;
        const uint32_t bar_k = bars + 8 * (k < B_W1 ? k : map == 4 ? B_W1 + i : B_W2 + i);
        const uint32_t dst = sb + 128 * (4 * lut10(pack10(OFF_WUK / 512, OFF_CK0 / 512, OFF_WQ / 512, OFF_WUK / 512, OFF_W1 / 512, OFF_W2 / 512))
                                         + i * lut8(pack8(64, 64, 64, 64, 30, 40)));
        const uint32_t c0 = map == 4 ? 72 * kap + 32 * r : 0;
        const uint32_t c1 = map == 1 ? 128 * kap + 64 * (i >> 3) : map == 3 ? 128 * h + 64 * r : map == 4 ? 48 * i : map == 5 ? 36 * b : 128 * j + 32 * i;
        const uint32_t c2 = map == 1 ? (i & 7) : map == 4 ? 0 : (map & 1) ? i : 2 * h;
        const uint32_t gate = map < 2 ? 0 : map == 2 ? B_FREE_A : map == 3 ? (i < 4 ? B_FREE_B : B_FREE_C0) : B_LATE;
        const uint32_t mode = map == 1 ? (((i & 1) == r) ? 1 : 2) : k < NOPS ? 0 : 2;
        const int pre = k < B_W1 ? (int)(lut10(pack10(72, 136, 264, 328, 0, 0)) + i * lut8(pack8(16, 8, 16, 8, 0, 0))) : 400;
        const uint32_t due = t0 + (uint32_t)max(0, (pre - 2 * PACE_PRE) * PACE_NS_PER_KB / 2);
        const int lag = k < B_W1 ? k - PACE_LAG : -1;
        const void* tm = &maps.m[map];
        __syncwarp();
        asm volatile("barrier.cluster.arrive.relaxed.aligned;" ::: "memory");
#pragma unroll 1
        for (int L = 0; L < (NOPS + NPROD - 1) / NPROD; L++) {
            if (L == 1) asm volatile("barrier.cluster.wait.aligned;" ::: "memory");
            if (lane == L && k < NOPS) {
                if (lag >= 0) mbar_wait(bars + 8 * lag);
                if (gate) mbar_wait(bars + 8 * gate);
                uint32_t due2 = due;
                if (k >= B_W1) {
                    const uint32_t tg = lds32(sb + OFF_TG) + (uint32_t)(js * LATE_NS);
                    if ((int)(tg - due2) > 0) due2 = tg;
                }
                while (true) {
                    uint32_t now; asm volatile("mov.u32 %0, %%globaltimer_lo;" : "=r"(now));
                    if ((int)(now - due2) >= 0) break;
                }
                if (mode == 0) tma3(dst, tm, c0, c1, c2, bar_k);
                else if (mode == 1) tma3_mc(dst, tm, 0, c1, c2, bar_k);
            }
            __syncwarp();
        }
        return;
    }

    const int g8 = lane >> 2, q4 = lane & 3;
    const int mat = lane >> 3, r8 = lane & 7;
    const uint32_t ta_off = ((mat >> 1) * 8 + r8) * 128 + ((((warp & 3) * 2 + (mat & 1)) ^ r8) << 4);
    const uint32_t zero_a = sb + OFF_CONST + mat * 16, ones_a = zero_a + 352;
    auto bvec = [&](uint32_t hi, uint32_t lo) { return r8 == 0 ? hi + mat * 16 : r8 == 1 ? lo + mat * 16 : zero_a; };
    uint2 xw = make_uint2(0, 0);
    if (tid < 144) xw = __ldg(x + tid);
    uint32_t epoch; asm volatile("ld.relaxed.gpu.global.u32 %0, [%1];" : "=r"(epoch) : "l"(G->epoch) : "memory");
    {
        if (warp < 8) {
            const uint8_t* src = wq + (size_t)(144 * j + (tid >> 4)) * 8192 + h * 256 + (tid & 15) * 16;
            const uint32_t dst = sb + OFF_WQ + ((tid >> 3) & 1) * 18432 + (tid >> 4) * 128 + (((tid & 7) ^ ((tid >> 4) & 7)) << 4);
#pragma unroll
            for (int i = 0; i < 9; i++)
                asm volatile("cp.async.cg.shared.global [%0], [%1], 16;" :: "r"(dst + i * 2048), "l"(src + (size_t)i * 16 * 8192) : "memory");
        }
        if (warp == 8) {
#pragma unroll
            for (int i = 0; i < 4; i++) sts128(sb + OFF_PB + (lane + 32 * i) * 16, make_uint4(0, 0, 0, 0));
            fence_proxy_async();
            __syncwarp();
            if (elect()) {
#pragma unroll 1
                for (int i = 0; i < 8; i++) bulk_store(G->part + b * 64 * 64 + i * 512, sb + OFF_PB, 2048);
                if (b < 14) bulk_store(G->acc + b * 512, sb + OFF_PB, 2048);
                bulk_commit();
            }
        }
        if (lane == 0) {
#pragma unroll 1
            for (int i = NPROD + warp; i < NOPS; i += 9) mbar_init(bars + 8 * i, 1);
            if (warp < 5) mbar_init(bars + 8 * (B_FREE_A + warp), warp == 3 ? 5 : warp == 4 ? 1 : 8);
            asm volatile("fence.mbarrier_init.release.cluster;" ::: "memory");
#pragma unroll 1
            for (int i = NPROD + warp; i < NOPS; i += 9) mbar_expect_tx(bars + 8 * i, i < B_W1 ? 8192u : i < B_W2 ? 3840u : 5120u);
            if (warp == 3) mbar_expect_tx(bars + 8 * B_CTX, 256);
        }
        if (tid < 176) sts32(sb + OFF_CONST + tid * 4, tid < 88 ? 0u : 0x3F803F80u);
        if (tid >= 192 && tid < 196) sts32(sb + OFF_ST + 40 + (tid - 192) * 4, 0u);
        __syncwarp();
        asm volatile("barrier.cluster.arrive.relaxed.aligned;" ::: "memory");
        if (warp < 5) {
            if (tid < 144) *reinterpret_cast<uint2*>(smem_raw + OFF_HB + tid * 8) = xw;
            publish_stats(bf_lo(xw.x), bf_hi(xw.x), bf_lo(xw.y), bf_hi(xw.y), sb, tid);
        }
        bar_sync(1, NC);
    }
    const uint32_t tag = (epoch + 1) & 1;
    const uint32_t* const qa_p = G->qa + (16 * r) * (DC / 2) + (tid & 255) * 4;
    Quad qv;

    if (warp < 8) {
        uint32_t bb[5][4];
        {
            const uint32_t xb = bvec(sb + OFF_HB + 288 * j, sb + OFF_CONST + 352);
#pragma unroll
            for (int p = 0; p < 5; p++) ldsm4(bb[p], xb + p * 64);
        }
        const float2 mr = ln_stats(sb);
        asm volatile("cp.async.wait_all;" ::: "memory");
        bar_sync(6, 256);
        float ac[3][4] = {};
        const uint32_t ab = sb + OFF_WQ + (warp >> 2) * 18432 + ta_off;
#pragma unroll
        for (int s = 0; s < 9; s++) {
            uint32_t a[4]; ldsm4t(a, ab + s * 2048);
            mma16816(ac[s % 3], a, bb[s >> 1][(s & 1) * 2], bb[s >> 1][(s & 1) * 2 + 1]);
        }
        if (q4 == 0) {
            const uint32_t v0 = nzf(((ac[0][0] + ac[1][0] + ac[2][0]) - mr.x * (ac[0][1] + ac[1][1] + ac[2][1])) * mr.y);
            const uint32_t v1 = nzf(((ac[0][2] + ac[1][2] + ac[2][2]) - mr.x * (ac[0][3] + ac[1][3] + ac[2][3])) * mr.y);
            uint32_t* p = G->qp + (h * 4 + j) * HD + 16 * warp + g8;
            st_pub1(p, v0); st_pub1(p + 8, v1);
            sts32(sb + OFF_QX + (16 * warp + g8) * 4, v0); sts32(sb + OFF_QX + (16 * warp + g8 + 8) * 4, v1);
        }
        __syncwarp();
        if (lane == 0) mbar_arrive(bars + 8 * B_FREE_A);
        bar_arrive(8, NC);
        qv = load_quad(qa_p, 1024);
    }

    const uint32_t vb = bvec(sb + OFF_VB, sb + OFF_VB + VB_LO);
    {
        uint32_t a[8][4];
        if (warp < 8) {
            mbar_wait_inline(bars + 8 * (B_WUK + (warp >> 1)));
            const int row = (warp & 1) * 16 + (mat & 1) * 8 + r8;
            const uint32_t ab = sb + OFF_WUK + (warp >> 1) * 8192 + row * 128 + (((mat >> 1) ^ r8) << 4);
#pragma unroll
            for (int s = 0; s < 8; s++) ldsm4(a[s], (ab ^ ((s & 3) << 5)) + (s >> 2) * 4096);
        } else {
            const uint32_t* p = G->qp + h * 4 * HD + lane * 4;
            Quad f = load_quad(p, HD);
            bar_sync(8, NC);
            { const uint4 own = lds128(sb + OFF_QX + lane * 16); if (j == 0) f.a = own; else if (j == 1) f.b = own; else if (j == 2) f.c = own; else f.d = own; }
            const Quad qq = poll_quad(f, p, HD, now_ns(), Q_DELAY);
            const uint4 v0 = qq.a, v1 = qq.b, v2 = qq.c, v3 = qq.d;
            const float sc = 0.08838834764831845f * 1.4426950408889634f;
            const float q0 = (__uint_as_float(v0.x) + __uint_as_float(v1.x) + __uint_as_float(v2.x) + __uint_as_float(v3.x)) * sc;
            const float q1 = (__uint_as_float(v0.y) + __uint_as_float(v1.y) + __uint_as_float(v2.y) + __uint_as_float(v3.y)) * sc;
            const float q2 = (__uint_as_float(v0.z) + __uint_as_float(v1.z) + __uint_as_float(v2.z) + __uint_as_float(v3.z)) * sc;
            const float q3 = (__uint_as_float(v0.w) + __uint_as_float(v1.w) + __uint_as_float(v2.w) + __uint_as_float(v3.w)) * sc;
            uint32_t h0, l0, h1, l1; split2(q0, q1, h0, l0); split2(q2, q3, h1, l1);
            sts64(sb + OFF_VB + lane * 8, h0, h1); sts64(sb + OFF_VB + VB_LO + lane * 8, l0, l1);
            asm volatile("cp.async.bulk.wait_group 0;" ::: "memory");
        }
        bar_sync(1, NC);
        if (warp < 8) {
            float acc[4][4] = {};
            uint32_t bb[4][4];
#pragma unroll
            for (int p = 0; p < 4; p++) ldsm4(bb[p], vb + p * 64);
#pragma unroll
            for (int s = 0; s < 8; s++) mma16816(acc[s & 3], a[s], bb[s >> 1][(s & 1) * 2], bb[s >> 1][(s & 1) * 2 + 1]);
            const float v0 = ((acc[0][0] + acc[0][1]) + (acc[1][0] + acc[1][1])) + ((acc[2][0] + acc[2][1]) + (acc[3][0] + acc[3][1]));
            const float v1 = ((acc[0][2] + acc[0][3]) + (acc[1][2] + acc[1][3])) + ((acc[2][2] + acc[2][3]) + (acc[3][2] + acc[3][3]));
            const uint32_t w0 = pack_bf16(v0, __shfl_down_sync(~0u, v0, 4)), w1 = pack_bf16(v1, __shfl_down_sync(~0u, v1, 4));
            const uint32_t x0 = __shfl_sync(~0u, w0, 8 * (lane & 3)), x1 = __shfl_sync(~0u, w1, 8 * (lane & 3));
            if (lane < 8) st_pub1(G->qa + (h * DC + 128 * j + 16 * warp) / 2 + lane, nz(lane < 4 ? x0 : x1));
            if (lane == 0) mbar_arrive(bars + 8 * B_FREE_B);
        }
    }
    uint32_t t_written = 0;
    asm volatile("barrier.cluster.wait.aligned;" ::: "memory");

    if (warp < 8) {
        {
            const int hd4 = tid >> 6, u64 = tid & 63;
            { const uint32_t t1 = now_ns(); const int d = max(A_MIN, min(A_DELAY, A_ABS - (int)(t1 - t_kernel)));
              qv = poll_quad(qv, qa_p, 1024, t1, d); }
            const uint32_t d = sb + OFF_QA + (u64 >> 3) * 2048 + hd4 * 128 + (((u64 & 7) ^ hd4) << 4);
            sts128(d, qv.a); sts128((d ^ 64) + 512, qv.b); sts128(d + 1024, qv.c); sts128((d ^ 64) + 1536, qv.d);
            fence_proxy_async();
            bar_sync(6, 256);
        }

        const int wg = warp >> 2, wq = warp & 3;
        float s[8];
        {
            const uint32_t da = desc_lo(sb + OFF_CK0 + wg * 65536), db = desc_lo(sb + OFF_QA);
            wg_fence();
#pragma unroll 1
            for (int g = 0; g < 8; g++) {
                mbar_wait_inline(bars + 8 * (B_CK + wg * 8 + g));
#pragma unroll
                for (int k = 0; k < 4; k++) wgmma16<0>(s, da + g * 512 + k * 2, db + g * 128 + k * 2, g | k);
            }
            wg_commit(); wg_wait0(); pin(s);
        }
        float m[4] = {fmaxf(s[0], s[2]), fmaxf(s[1], s[3]), fmaxf(s[4], s[6]), fmaxf(s[5], s[7])};
#pragma unroll
        for (int o = 4; o <= 16; o <<= 1) {
#pragma unroll
            for (int i = 0; i < 4; i++) m[i] = fmaxf(m[i], __shfl_xor_sync(~0u, m[i], o));
        }
        if (g8 == 0) stsf4(sb + OFF_SMAX + warp * 64 + q4 * 16, m[0], m[1], m[2], m[3]);
        bar_sync(2 + wg, 128);
        if (wg == 0) bar_arrive(4, 256); else bar_sync(4, 256);
        {
            const float4 u = ldsf4(sb + OFF_SMAX + (wg ? g8 : (g8 & 3)) * 64 + q4 * 16);
            m[0] = u.x; m[1] = u.y; m[2] = u.z; m[3] = u.w;
#pragma unroll
            for (int o = 4; o <= 16; o <<= 1) {
#pragma unroll
                for (int i = 0; i < 4; i++) m[i] = fmaxf(m[i], __shfl_xor_sync(~0u, m[i], o));
            }
        }
        {
            const float p0 = ex2(s[0] - m[0]), p1 = ex2(s[1] - m[1]), p2 = ex2(s[2] - m[0]), p3 = ex2(s[3] - m[1]);
            const float p4 = ex2(s[4] - m[2]), p5 = ex2(s[5] - m[3]), p6 = ex2(s[6] - m[2]), p7 = ex2(s[7] - m[3]);
            stsm4t(sb + OFF_P + wg * 2048 + ((mat >> 1) * 8 + r8) * 128 + (((2 * wq + (mat & 1)) ^ r8) << 4),
                   pack_bf16(p0, p1), pack_bf16(p2, p3), pack_bf16(p4, p5), pack_bf16(p6, p7));
            if (wq == 0 && g8 == 0) {
                const uint32_t d = sb + OFF_MX + wg * 64 + q4 * 8;
                stsf2(d, m[0], m[1]); stsf2(d + 32, m[2], m[3]);
            }
        }
        if (wg == 1) {
            bar_arrive(5, 256);
        } else {
            float o[16][4] = {}, ls[4] = {};
            const uint32_t fa = ((mat & 1) * 8 + r8) * 128 + (((mat >> 1) ^ r8) << 4);
#pragma unroll 1
            for (int t = 0; t < 2; t++) {
                if (t == 0) bar_sync(2, 128);
                else {
                    bar_sync(5, 256);
                    const float a0 = ex2(ldsf(sb + OFF_MX + g8 * 4) - ldsf(sb + OFF_MX + 64 + g8 * 4));
                    const float a1 = ex2(ldsf(sb + OFF_MX + 32 + g8 * 4) - ldsf(sb + OFF_MX + 96 + g8 * 4));
#pragma unroll
                    for (int n = 0; n < 16; n++) { o[n][0] *= a0; o[n][1] *= a0; o[n][2] *= a1; o[n][3] *= a1; }
                    ls[0] *= a0; ls[2] *= a1;
                }
                const uint32_t pa = sb + OFF_P + t * 2048 + fa, pb = sb + OFF_CK0 + t * 65536 + wq * 16384 + fa;
#pragma unroll
                for (int k = 0; k < 4; k++) {
                    uint32_t a[4]; ldsm4(a, pa ^ (k << 5));
                    if (warp == 0) mma16816(ls, a, 0x3F803F80u, 0x3F803F80u);
#pragma unroll
                    for (int np = 0; np < 8; np++) {
                        uint32_t c[4]; ldsm4t(c, (pb ^ ((np & 3) << 5)) + (np >> 2) * 8192 + k * 2048);
                        mma16816(o[2 * np], a, c[0], c[1]); mma16816(o[2 * np + 1], a, c[2], c[3]);
                    }
                }
                if (lane == 0 && t == 0) { mbar_arrive(bars + 8 * B_FREE_C0); mbar_arrive(bars + 8 * B_FREE_C0); }
            }
            if (warp == 0) {
                uint32_t* p = G->ml + (((16 * r + g8) * 4 + q4) * 64 + kap) * 32;
                st_pub2(p, tagf(ldsf(sb + OFF_MX + 64 + g8 * 4), tag), tagf(ls[0], tag));
                st_pub2(p + 8 * 4 * 64 * 32, tagf(ldsf(sb + OFF_MX + 96 + g8 * 4), tag), tagf(ls[2], tag));
            }
            const uint32_t sw = sb + OFF_SG + wq * 4096 + fa;
#pragma unroll
            for (int np = 0; np < 8; np++)
                stsm4((sw ^ ((np & 3) << 5)) + (np >> 2) * 2048, pack_nz(o[2 * np][0], o[2 * np][1]), pack_nz(o[2 * np][2], o[2 * np][3]),
                      pack_nz(o[2 * np + 1][0], o[2 * np + 1][1]), pack_nz(o[2 * np + 1][2], o[2 * np + 1][3]));
        }
        bar_sync(6, 256);
        {
            const uint32_t st = sb + OFF_SG + warp * 2048;
            uint32_t* gp = G->part + ((((16 * r + mat) * 4 + (warp >> 1)) * 64 + kap) * 16 + (warp & 1) * 8 + r8) * 4;
#pragma unroll
            for (int i = 0; i < 4; i++) st_pub4(gp + i * (4 * 4 * 64 * 64), lds128(st + (mat + 4 * i) * 128 + ((r8 ^ ((mat + 4 * i) & 7)) << 4)));
        }
        t_written = now_ns();
    }

    uint32_t wo[4][4][4], wo8[4][2];
    {
        uint32_t a[8][4];
        if (warp < 8) {
#pragma unroll
            for (int i = 0; i < 4; i++) {
                mbar_wait(bars + 8 * (B_WUV + i));
                ldsm4t(a[2 * i], sb + OFF_WQ + i * 8192 + (warp >> 2) * 4096 + ta_off);
                ldsm4t(a[2 * i + 1], sb + OFF_WQ + i * 8192 + (warp >> 2) * 4096 + ta_off + 2048);
            }
        } else {
            const uint32_t* pm = G->ml + (b * 64 + 2 * lane) * 32;
            uint2 va = ld_poll2(pm), vb2 = ld_poll2(pm + 32); int n = 0;
            bar_sync(7, NC);
            const uint32_t t_ml = now_ns();
            while (!poll_done(tagged(make_uint4(va.x, va.y, vb2.x, vb2.y), tag), n)) { if (n == 1) wait_until(t_ml, ML_DELAY); va = ld_poll2(pm); vb2 = ld_poll2(pm + 32); }
            const uint4 v = make_uint4(va.x, va.y, vb2.x, vb2.y);
            const float m0 = __uint_as_float(v.x), m1 = __uint_as_float(v.z);
            float mx = fmaxf(m0, m1);
#pragma unroll
            for (int o = 16; o; o >>= 1) mx = fmaxf(mx, __shfl_xor_sync(~0u, mx, o));
            const float w0 = ex2(m0 - mx), w1 = ex2(m1 - mx);
            float lt = w0 * __uint_as_float(v.y) + w1 * __uint_as_float(v.w);
#pragma unroll
            for (int o = 16; o; o >>= 1) lt += __shfl_xor_sync(~0u, lt, o);
            const float inv = __fdividef(1.f, lt);
            uint32_t hi, lo; split2(w0 * inv, w1 * inv, hi, lo);
            sts32(sb + OFF_WS + lane * 4, hi); sts32(sb + OFF_WS + WS_LO + lane * 4, lo);
        }
        if (warp < 8) {
            bar_sync(7, NC);
            if (tid == 0) open_late_gate(sb);
            const uint32_t* pp = G->part + (h * 4 + j) * 64 * 64 + tid * 4;
            { const int d = max(B_MIN, min(B_DELAY, B_ABS - (int)(t_written - t_kernel)));
              while ((int)(now_ns() - t_written) < d) {} }
            const Quad look = load_quad(pp, 1024);
            mbar_wait_inline(bars + 8 * (B_WO + warp));
            out_proj_load<4, false>(wo, wo8, sb + OFF_WUK + warp * 8192, mat, r8);
            const Quad v = poll_quad_inl(look, pp, 1024, t_written, 0);
            const uint32_t d = sb + OFF_SG + ((tid >> 3) & 1) * 8192 + (tid >> 4) * 128 + (((tid & 7) ^ ((tid >> 4) & 7)) << 4);
            sts128(d, v.a); sts128(d + 2048, v.b); sts128(d + 4096, v.c); sts128(d + 6144, v.d);
            if (warp == 1) *reinterpret_cast<uint4*>(G->qp + (h * 4 + j) * HD + lane * 4) = make_uint4(0, 0, 0, 0);
            if (warp == 2 && lane < 16) *reinterpret_cast<uint4*>(G->qa + (h * DC + 128 * j) / 2 + lane * 4) = make_uint4(0, 0, 0, 0);
        }
        bar_sync(1, NC);
        if (warp < 8) {
            float o[4][4] = {};
            const uint32_t wb = bvec(sb + OFF_WS, sb + OFF_WS + WS_LO);
            uint32_t wf[2][4]; ldsm4(wf[0], wb); ldsm4(wf[1], wb + 64);
#pragma unroll
            for (int s = 0; s < 4; s++) {
                uint32_t c[4]; ldsm4t(c, sb + OFF_SG + (warp >> 2) * 8192 + ta_off + s * 2048);
                mma16816(o[s], c, wf[s >> 1][(s & 1) * 2], wf[s >> 1][(s & 1) * 2 + 1]);
            }
            const float v0 = ((o[0][0] + o[0][1]) + (o[1][0] + o[1][1])) + ((o[2][0] + o[2][1]) + (o[3][0] + o[3][1]));
            const float v1 = ((o[0][2] + o[0][3]) + (o[1][2] + o[1][3])) + ((o[2][2] + o[2][3]) + (o[3][2] + o[3][3]));
            uint32_t h0, l0, h1, l1;
            split2(v0, __shfl_down_sync(~0u, v0, 4), h0, l0); split2(v1, __shfl_down_sync(~0u, v1, 4), h1, l1);
            if (r8 == 0) {
                const uint32_t d = sb + OFF_VB + warp * 32 + mat * 4;
                sts32(d, h0); sts32(d + 16, h1); sts32(d + VB_LO, l0); sts32(d + VB_LO + 16, l1);
            }
            bar_sync(6, 256);
            float d[4][4] = {};
            uint32_t bb[4][4];
#pragma unroll
            for (int p = 0; p < 4; p++) ldsm4(bb[p], vb + p * 64);
#pragma unroll
            for (int s = 0; s < 8; s++) mma16816(d[s & 3], a[s], bb[s >> 1][(s & 1) * 2], bb[s >> 1][(s & 1) * 2 + 1]);
            if (q4 == 0) {
                const float c0 = ((d[0][0] + d[0][1]) + (d[1][0] + d[1][1])) + ((d[2][0] + d[2][1]) + (d[3][0] + d[3][1]));
                const float c1 = ((d[0][2] + d[0][3]) + (d[1][2] + d[1][3])) + ((d[2][2] + d[2][3]) + (d[3][2] + d[3][3]));
                const uint32_t la = sb + OFF_CTXP + r * 256 + ((warp & 3) * 16 + g8) * 4;
                if ((warp >> 2) == r) { stsf(la, c0); stsf(la + 32, c1); }
                else {
                    uint32_t ra, rb;
                    asm volatile("mapa.shared::cluster.u32 %0, %1, %2;" : "=r"(ra) : "r"(la), "r"(r ^ 1));
                    asm volatile("mapa.shared::cluster.u32 %0, %1, %2;" : "=r"(rb) : "r"(bars + 8 * B_CTX), "r"(r ^ 1));
                    asm volatile("st.async.weak.shared::cluster.mbarrier::complete_tx::bytes.f32 [%0], %1, [%2];" :: "r"(ra), "f"(c0), "r"(rb) : "memory");
                    asm volatile("st.async.weak.shared::cluster.mbarrier::complete_tx::bytes.f32 [%0], %1, [%2];" :: "r"(ra + 32), "f"(c1), "r"(rb) : "memory");
                }
            }
            __syncwarp();
            if ((warp >> 2) == r && lane == 0) mbar_arrive(bars + 8 * B_CTX);
        }
    }

    uint32_t* const outp = G->pp + (4 * warp * NCTA + b) * 32 + g8;
    const uint32_t* const red_p = G->pp + min(red, NRED - 1) * NCTA * 32 + ((tid & 255) >> 2) * 32 + (tid & 3) * 4;
    uint4 rv = make_uint4(0, 0, 0, 0), ru = rv;
    {
        if (warp == 8) {
            mbar_wait_inline(bars + 8 * (B_WO + 8));
            out_proj_load<4, false>(wo, wo8, sb + OFF_WUK + 8 * 8192, mat, r8);
        }
        if (warp == 8) {
            mbar_wait_cluster(bars + 8 * B_CTX);
            const float2 u = ldsf2(sb + OFF_CTXP + lane * 8), v = ldsf2(sb + OFF_CTXP + 256 + lane * 8);
            uint32_t hi, lo; split2(u.x + v.x, u.y + v.y, hi, lo);
            sts32(sb + OFF_WS + lane * 4, hi); sts32(sb + OFF_WS + WS_LO + lane * 4, lo);
        }
        bar_sync(1, NC);
        const uint32_t wb = bvec(sb + OFF_WS, sb + OFF_WS + WS_LO);
        uint32_t bb[2][4]; ldsm4(bb[0], wb); ldsm4(bb[1], wb + 64);
        float d[4][4] = {};
#pragma unroll
        for (int s = 0; s < 4; s++) {
#pragma unroll
            for (int t = 0; t < 4; t++) mma16816(d[t], wo[t][s], bb[s >> 1][(s & 1) * 2], bb[s >> 1][(s & 1) * 2 + 1]);
        }
        if (q4 == 0) {
            uint32_t* p = G->acc + (warp * 8 + g8) * 3 * 32;
            red4(p, d[0][0] + d[0][1], d[0][2] + d[0][3], d[1][0] + d[1][1]);
            red4(p + 32, d[1][2] + d[1][3], d[2][0] + d[2][1], d[2][2] + d[2][3]);
            red4(p + 64, d[3][0] + d[3][1], d[3][2] + d[3][3], 0.f);
        }
    }
    const uint32_t t_p5 = now_ns();

    {
        uint32_t a[4][3][4];
        mbar_wait_inline(bars + 8 * (B_W1 + (64 * warp) / 48)); mbar_wait_inline(bars + 8 * (B_W1 + (64 * warp + 63) / 48)); mbar_wait_inline(bars + 8 * (B_W1 + (64 * warp + 32) / 48));
        {
            const uint32_t ab = sb + OFF_W1 + (64 * warp + (mat >> 1) * 8 + r8) * 80 + (mat & 1) * 16;
#pragma unroll
            for (int t = 0; t < 4; t++) {
#pragma unroll
                for (int mt = 0; mt < 3; mt++) ldsm4t(a[t][mt], ab + t * 16 * 80 + mt * 32);
            }
        }
        float hs_ = 0.f, hq_ = 0.f;
        if (warp < 7) {
            const int t = min(tid, 215), wg_ = t / 3, k3 = t - 3 * wg_;
            const uint32_t* ap = G->acc + t * 32;
            uint4 v; int n = 0;
            wait_until(t_p5, H_DELAY);
            do { v = ld_poll4(ap); } while (!poll_done(__uint_as_float(v.w) == (float)NCTA, n));
            if (tid < 216) {
                const int col0 = 64 * (wg_ >> 3) + 24 * k3 + (wg_ & 7);
                const float a3[3] = {__uint_as_float(v.x), __uint_as_float(v.y), __uint_as_float(v.z)};
#pragma unroll
                for (int e = 0; e < 3; e++) {
                    if (e < 2 || k3 < 2) {
                        const int col = col0 + 8 * e;
                        uint16_t xb; asm volatile("ld.shared.u16 %0, [%1];" : "=h"(xb) : "r"(sb + OFF_HB + col * 2) : "memory");
                        const float hvv = __uint_as_float((uint32_t)xb << 16) + a3[e];
                        const uint32_t hi = pack_bf16(hvv, 0.f), lo = pack_bf16(hvv - bf_lo(hi), 0.f);
                        asm volatile("st.shared.u16 [%0], %1;" :: "r"(sb + OFF_HB + col * 2), "h"((uint16_t)hi) : "memory");
                        asm volatile("st.shared.u16 [%0], %1;" :: "r"(sb + OFF_HB + HB_LO + col * 2), "h"((uint16_t)lo) : "memory");
                        if ((col >> 4) == red) stsf(sb + OFF_ST + 80 + (col & 15) * 4, hvv);
                        hs_ += hvv; hq_ += hvv * hvv;
                    }
                }
            }
        }
        bar_sync(1, NC);
        if (red < NRED && warp < 8) { rv = ld_poll4(red_p); ru = ld_poll4(red_p + 64 * 32); }
        float d[3][4] = {};
        const uint32_t hb = r8 == 2 ? ones_a : bvec(sb + OFF_HB + warp * 128, sb + OFF_HB + HB_LO + warp * 128);
        uint32_t bb[2][4]; ldsm4(bb[0], hb); ldsm4(bb[1], hb + 64);
#pragma unroll
        for (int t = 0; t < 4; t++) {
#pragma unroll
            for (int mt = 0; mt < 3; mt++) mma16816(d[mt], a[t][mt], bb[t >> 1][(t & 1) * 2], bb[t >> 1][(t & 1) * 2 + 1]);
        }
        if (q4 < 2) {
            const uint32_t pa = sb + OFF_PB + 512 + (warp * 48 + g8) * 8 + q4 * 4;
#pragma unroll
            for (int mt = 0; mt < 3; mt++) {
                stsf(pa + mt * 128, q4 == 0 ? d[mt][0] + d[mt][1] : d[mt][0]);
                stsf(pa + mt * 128 + 64, q4 == 0 ? d[mt][2] + d[mt][3] : d[mt][2]);
            }
        }
        if (warp < 7) {
#pragma unroll
            for (int o = 16; o; o >>= 1) { hs_ += __shfl_xor_sync(~0u, hs_, o); hq_ += __shfl_xor_sync(~0u, hq_, o); }
            if (lane == 0) stsf2(sb + OFF_ST + warp * 8, hs_, hq_);
        }
        bar_sync(1, NC);
        if (tid < 24) {
            float4 s = make_float4(0, 0, 0, 0);
#pragma unroll
            for (int w = 0; w < 9; w++) {
                const float4 u = ldsf4(sb + OFF_PB + 512 + (w * 48 + 4 * r + 2 * tid) * 8);
                s.x += u.x; s.y += u.y; s.z += u.z; s.w += u.w;
            }
            const float2 mr = ln_stats(sb);
            float y0 = (s.x - mr.x * s.y) * mr.y, y1 = (s.z - mr.x * s.w) * mr.y;
            y0 = __fdividef(y0, 1.f + __expf(-y0)); y1 = __fdividef(y1, 1.f + __expf(-y1));
            uint32_t hi, lo; split2(y0, y1, hi, lo);
            sts32(sb + OFF_H1 + tid * 4, tid < 18 ? hi : 0u); sts32(sb + OFF_H1 + H1_LO + tid * 4, tid < 18 ? lo : 0u);
        }
    }

    {
        uint32_t a[4][2][4], a8[4][2];
        mbar_wait_inline(bars + 8 * (B_W2 + warp));
        out_proj_load<2, true>(a, a8, sb + OFF_W2 + warp * 5120, mat, r8);
        bar_sync(1, NC);
        const uint32_t hb = bvec(sb + OFF_H1, sb + OFF_H1 + H1_LO);
        uint32_t bb[4], b8[2]; ldsm4(bb, hb); ldsm2(b8, hb + 64);
        const uint32_t b0 = bb[0], b1 = bb[1], b2 = bb[2], b3 = bb[3], b4 = b8[0];
        float d[4][4] = {};
#pragma unroll
        for (int t = 0; t < 4; t++) mma16816(d[t], a[t][0], b0, b1);
#pragma unroll
        for (int t = 0; t < 4; t++) mma16816(d[t], a[t][1], b2, b3);
#pragma unroll
        for (int t = 0; t < 4; t++) mma1688(d[t], a8[t], b4);
        if (q4 == 0) {
#pragma unroll
            for (int t = 0; t < 4; t++) {
                st_pub1(outp + t * NCTA * 32, tagf(d[t][0] + d[t][1], tag)); st_pub1(outp + t * NCTA * 32 + 8, tagf(d[t][2] + d[t][3], tag));
            }
        }
    }
    const uint32_t t_p7 = now_ns();

    if (red < NRED && warp < 8) {
        float s = reduce_slice(rv, ru, red_p, sb + OFF_PB, tag, tid, t_p7, F_DELAY);
        if (tid < 16) out[red * 16 + tid] = __float2bfloat16_rn(s + ldsf(sb + OFF_ST + 80 + tid * 4));
        if (b == 0 && tid == 0) st_pub1(G->epoch, epoch + 1);
    }
}

typedef CUresult (*EncodeFn)(CUtensorMap*, CUtensorMapDataType, cuuint32_t, void*, const cuuint64_t*, const cuuint64_t*,
                             const cuuint32_t*, const cuuint32_t*, CUtensorMapInterleave, CUtensorMapSwizzle,
                             CUtensorMapL2promotion, CUtensorMapFloatOOBfill);

void make_map3(EncodeFn enc, CUtensorMap* m, const void* p, uint64_t rows, uint64_t row_bytes, uint32_t box_rows, uint32_t box_groups) {
    cuuint64_t dims[3] = {64, rows, row_bytes / 128};
    cuuint64_t strides[2] = {row_bytes, 128};
    cuuint32_t box[3] = {64, box_rows, box_groups};
    cuuint32_t es[3] = {1, 1, 1};
    enc(m, CU_TENSOR_MAP_DATA_TYPE_BFLOAT16, 3, const_cast<void*>(p), dims, strides, box, es, CU_TENSOR_MAP_INTERLEAVE_NONE,
        CU_TENSOR_MAP_SWIZZLE_128B, CU_TENSOR_MAP_L2_PROMOTION_NONE, CU_TENSOR_MAP_FLOAT_OOB_FILL_NONE);
}

}

extern "C" void kernel_launch(void* const* d_in, const int* in_sizes, int n_in, void* d_out, int out_size) {
    (void)in_sizes; (void)n_in; (void)out_size;
    static EncodeFn enc = nullptr;
    static Scratch* scratch = nullptr;
    if (!enc) {
        void* fn = nullptr; cudaDriverEntryPointQueryResult qr;
        cudaGetDriverEntryPoint("cuTensorMapEncodeTiled", &fn, cudaEnableDefault, &qr);
        enc = (EncodeFn)fn;
        cudaGetSymbolAddress((void**)&scratch, g_scratch);
        cudaFuncSetAttribute(fused_decode_kernel, cudaFuncAttributeMaxDynamicSharedMemorySize, SMEM_BYTES);
    }
    Maps maps;
    make_map3(enc, &maps.m[0], d_in[3], DC, NH * HD * 2, 32, 2);
    make_map3(enc, &maps.m[1], d_in[1], SK, DC * 2, 64, 1);
    make_map3(enc, &maps.m[2], d_in[4], DC, NH * HD * 2, 32, 2);
    make_map3(enc, &maps.m[3], d_in[5], NH * HD, DM * 2, 64, 1);
    make_map3(enc, &maps.m[5], d_in[8], DF, DM * 2, 40, 1);
    {
        cuuint64_t dims[3] = {DF, DM, 1}; cuuint64_t strides[2] = {DF * 2, (cuuint64_t)DF * 2 * DM};
        cuuint32_t box[3] = {40, 48, 1}; cuuint32_t es[3] = {1, 1, 1};
        enc(&maps.m[4], CU_TENSOR_MAP_DATA_TYPE_BFLOAT16, 3, d_in[7], dims, strides, box, es, CU_TENSOR_MAP_INTERLEAVE_NONE,
            CU_TENSOR_MAP_SWIZZLE_NONE, CU_TENSOR_MAP_L2_PROMOTION_L2_256B, CU_TENSOR_MAP_FLOAT_OOB_FILL_NONE);
    }
    fused_decode_kernel<<<NCTA, NTHREADS, SMEM_BYTES>>>(maps, (const uint2*)d_in[0], (const uint8_t*)d_in[2], (__nv_bfloat16*)d_out, scratch);
}
```
